```python
import torch

def _softmax(x, axis=-1):
    return torch.softmax(x, dim=axis)
def _gelu(x):
    return torch.nn.functional.gelu(x, approximate="tanh")
def _silu(x):
    return torch.nn.functional.silu(x)
def _sigmoid(x):
    return torch.sigmoid(x)
def _layernorm(x, axis=-1, eps=1e-5):
    m = x.mean(dim=axis, keepdim=True)
    v = x.var(dim=axis, keepdim=True, unbiased=False)
    return (x - m) / torch.sqrt(v + eps)
def _scatter_add(tgt, idx, src, axis=0):
    return tgt.clone().index_add_(axis, idx, src)
def _segment_sum(src, seg, n):
    out = torch.zeros((n,) + src.shape[1:], dtype=src.dtype)
    return out.index_add_(0, seg, src)
def _pad(x, pw):
    flat = tuple(v for pair in reversed(pw) for v in pair)
    return torch.nn.functional.pad(x, flat)

kernel_name = 'standalone__kv_cache_quant_int4_int2_kv_with_per_channel_or_per_token_scales__prompt'

def setup_inputs():

    _w = (lambda a: (lambda t: t.to(torch.bfloat16) if t.is_floating_point() else t)(torch.as_tensor(a)))
    B = 1
    Sq = 2048
    Skv = 2048
    Hq = 32
    Hkv = 32
    Dh = 128
    bits = 2
    G = 64
    if G <= 0 or G >= Skv:
        G = max(1, Skv // 2)
    Skv = (Skv // G) * G
    ngk = Skv // G
    qmax = (1 << bits) - 1
    return {
        "q": _w((lambda *s: torch.randn(*s, dtype=torch.bfloat16) * 1.6)(B, Hq, Sq, Dh)),
        "qk": _w(torch.randint(0, qmax + 1, (B, Hkv, Skv, Dh)).to(torch.int32)),
        "qv": _w(torch.randint(0, qmax + 1, (B, Hkv, Skv, Dh)).to(torch.int32)),
        "k_scales": _w(torch.abs((lambda *s: torch.randn(*s, dtype=torch.bfloat16) * 1.6)(B, Hkv, ngk, Dh)) * 0.05 + 0.02),
        "k_zeros": _w((lambda *s: torch.randn(*s, dtype=torch.bfloat16) * 1.6)(B, Hkv, ngk, Dh) + float(qmax) / 2.0),
        "v_scales": _w(torch.abs((lambda *s: torch.randn(*s, dtype=torch.bfloat16) * 0.05)(B, Hkv, Skv, 1)) * 0.05 + 0.02),
        "v_zeros": _w((lambda *s: torch.randn(*s, dtype=torch.bfloat16) * 0.05)(B, Hkv, Skv, 1) + float(qmax) / 2.0),
    }

def reference(q, qk, qv, k_scales, k_zeros, v_scales, v_zeros):
    B, Hq, Sq, Dh = q.shape
    Hkv, Skv = qk.shape[1], qk.shape[2]
    ngk = k_scales.shape[2]
    G = Skv // ngk
    ks = (lambda x, n, axis: torch.repeat_interleave(x, n, dim=axis))(k_scales, G, axis=2)
    kz = (lambda x, n, axis: torch.repeat_interleave(x, n, dim=axis))(k_zeros, G, axis=2)
    k = ((lambda x, dt: x.to(dt))(qk, q.dtype) - kz) * ks
    v = ((lambda x, dt: x.to(dt))(qv, q.dtype) - v_zeros) * v_scales
    rep = Hq // Hkv
    if rep > 1:
        k = (lambda x, n, axis: torch.repeat_interleave(x, n, dim=axis))(k, rep, axis=1)
        v = (lambda x, n, axis: torch.repeat_interleave(x, n, dim=axis))(v, rep, axis=1)
    scale = float(Dh) ** -0.5
    logits = torch.einsum("bhqd,bhkd->bhqk", q, k) * scale
    p = _softmax(logits, axis=-1)
    o = torch.einsum("bhqk,bhkd->bhqd", p, v)
    return o
```

```cpp
#include <cuda_runtime.h>
#include <cuda_bf16.h>
#include <cuda.h>
#include <stdint.h>

namespace {

constexpr int NH = 32, SEQ = 2048, HD = 128, GRP = 64, NGRP = SEQ / GRP;
constexpr int BM = 128, BN = 128;
constexpr int NKV = SEQ / BN;
constexpr int TILE_BYTES = BN * HD * 2;
constexpr int HALF_BYTES = TILE_BYTES / 2;
#define KST 2
#define VST 2
#define CLUSTER 2
#define PINGPONG 1
constexpr int NUM_TILES = NH * (SEQ / BM);
constexpr int CTAS_PER_HEAD = SEQ / BM;

constexpr int JOB_ROWS = 8, JOBS_PER_UNIT = BN / JOB_ROWS;
constexpr int DQ_WARPS = 2;
constexpr int DQ_SLOTS = 3;
constexpr int DQ_SLOT_BYTES = JOB_ROWS * HD * 4 + 512;
#define DQ_LEAD 16
#define POLL_NS 20
#define QMODE 0
#define EARLY_STAGE 0
#define STARTUP_JOBS 2
#define FIXMAX 0
#define CREGS 224
#define PREGS 56

__device__ unsigned g_flags[NH * NKV * 2];
__device__ unsigned g_epoch, g_ticket;

__device__ __align__(1024) uint4 g_kd[NH * SEQ * HD / 8];
__device__ __align__(1024) uint4 g_vd[NH * SEQ * HD / 8];

__device__ __forceinline__ uint32_t smem_u32(const void* p) { return (uint32_t)__cvta_generic_to_shared(p); }
__device__ __forceinline__ void mbar_init(uint32_t bar, uint32_t cnt) { asm volatile("mbarrier.init.shared::cta.b64 [%0], %1;" ::"r"(bar), "r"(cnt)); }
__device__ __forceinline__ void mbar_expect_tx(uint32_t bar, uint32_t bytes) {
    asm volatile("mbarrier.arrive.expect_tx.shared::cta.b64 _, [%0], %1;" ::"r"(bar), "r"(bytes) : "memory");
}
__device__ __forceinline__ void mbar_arrive(uint32_t bar) { asm volatile("mbarrier.arrive.shared::cta.b64 _, [%0];" ::"r"(bar) : "memory"); }
__device__ __forceinline__ void mbar_arrive_cluster(uint32_t bar, uint32_t cta) {
    asm volatile("{\n.reg .b32 ra;\nmapa.shared::cluster.u32 ra, %0, %1;\nmbarrier.arrive.shared::cluster.b64 _, [ra];\n}" ::"r"(bar), "r"(cta) : "memory");
}
__device__ __forceinline__ uint32_t mbar_try(uint32_t bar, uint32_t parity) {
    uint32_t ok;
    asm volatile("{\n.reg .pred p;\nmbarrier.try_wait.parity.shared::cta.b64 p, [%1], %2;\nselp.u32 %0, 1, 0, p;\n}" : "=r"(ok) : "r"(bar), "r"(parity) : "memory");
    return ok;
}
__device__ __forceinline__ uint32_t mbar_test(uint32_t bar, uint32_t parity) {
    uint32_t ok;
    asm volatile("{\n.reg .pred p;\nmbarrier.test_wait.parity.shared::cta.b64 p, [%1], %2;\nselp.u32 %0, 1, 0, p;\n}" : "=r"(ok) : "r"(bar), "r"(parity) : "memory");
    return ok;
}
__shared__ int s_abort;
__device__ __forceinline__ void mbar_wait(uint32_t bar, uint32_t parity) {
    if (mbar_try(bar, parity)) return;
    const long long t0 = clock64();
    while (!mbar_try(bar, parity)) {
        if (clock64() - t0 > 2000000000LL || *(volatile int*)&s_abort) { *(volatile int*)&s_abort = 1; break; }
    }
}
#define SLEEP_NS 100
__device__ __forceinline__ void mbar_wait_sleep(uint32_t bar, uint32_t parity) {
    for (int n = 0; n < 10000000; n++) {
        if (mbar_test(bar, parity)) return;
        __nanosleep(SLEEP_NS);
        if (*(volatile int*)&s_abort) return;
    }
    *(volatile int*)&s_abort = 1;
}
__device__ __forceinline__ void bulk_load(uint32_t dst, const void* src, uint32_t bytes, uint32_t bar) {
    asm volatile("cp.async.bulk.shared::cluster.global.mbarrier::complete_tx::bytes [%0], [%1], %2, [%3];" ::"r"(dst), "l"(src), "r"(bytes), "r"(bar) : "memory");
}
__device__ __forceinline__ void bulk_load_mc(uint32_t dst, const void* src, uint32_t bytes, uint32_t bar, uint16_t mask) {
    asm volatile("cp.async.bulk.shared::cluster.global.mbarrier::complete_tx::bytes.multicast::cluster [%0], [%1], %2, [%3], %4;" ::"r"(dst), "l"(src), "r"(bytes), "r"(bar), "h"(mask) : "memory");
}
__device__ __forceinline__ void tma_load_2d(uint32_t dst, const CUtensorMap* map, int c0, int c1, uint32_t bar) {
    asm volatile("cp.async.bulk.tensor.2d.shared::cluster.global.mbarrier::complete_tx::bytes [%0], [%1, {%3, %4}], [%2];" ::"r"(dst), "l"(map), "r"(bar), "r"(c0), "r"(c1) : "memory");
}
__device__ __forceinline__ void tma_store_2d(const CUtensorMap* map, uint32_t src, int c0, int c1) {
    asm volatile("cp.async.bulk.tensor.2d.global.shared::cta.bulk_group [%0, {%2, %3}], [%1];" ::"l"(map), "r"(src), "r"(c0), "r"(c1) : "memory");
}
__device__ __forceinline__ void bulk_commit() { asm volatile("cp.async.bulk.commit_group;" ::: "memory"); }
__device__ __forceinline__ void bulk_wait_read() { asm volatile("cp.async.bulk.wait_group.read 0;" ::: "memory"); }
__device__ __forceinline__ void bulk_wait_all() { asm volatile("cp.async.bulk.wait_group 0;" ::: "memory"); }
__device__ __forceinline__ void fence_async_smem() { asm volatile("fence.proxy.async.shared::cta;" ::: "memory"); }
__device__ __forceinline__ void named_sync(int id, int n) { asm volatile("bar.sync %0, %1;" ::"r"(id), "r"(n) : "memory"); }
__device__ __forceinline__ void named_arrive(int id, int n) { asm volatile("bar.arrive %0, %1;" ::"r"(id), "r"(n) : "memory"); }
__device__ __forceinline__ void cluster_sync() { asm volatile("barrier.cluster.arrive.release.aligned;\nbarrier.cluster.wait.acquire.aligned;" ::: "memory"); }
__device__ __forceinline__ void wg_fence() { asm volatile("wgmma.fence.sync.aligned;" ::: "memory"); }
__device__ __forceinline__ void wg_commit() { asm volatile("wgmma.commit_group.sync.aligned;" ::: "memory"); }
template <int N> __device__ __forceinline__ void wg_wait() { asm volatile("wgmma.wait_group.sync.aligned %0;" ::"n"(N) : "memory"); }
template <int N> __device__ __forceinline__ void pin(float (&r)[N]) {
#pragma unroll
    for (int i = 0; i < N; i++) asm volatile("" : "+f"(r[i])::"memory");
}
template <int N> __device__ __forceinline__ void pin(uint32_t (&r)[N]) {
#pragma unroll
    for (int i = 0; i < N; i++) asm volatile("" : "+r"(r[i])::"memory");
}
__device__ __forceinline__ float ex2(float x) { float y; asm("ex2.approx.ftz.f32 %0, %1;" : "=f"(y) : "f"(x)); return y; }
__device__ __forceinline__ uint32_t pack_bf16(float lo, float hi) { uint32_t r; asm("cvt.rn.bf16x2.f32 %0, %1, %2;" : "=r"(r) : "f"(hi), "f"(lo)); return r; }
__device__ __forceinline__ void stmatrix_x4(uint32_t addr, uint32_t r0, uint32_t r1, uint32_t r2, uint32_t r3) {
    asm volatile("stmatrix.sync.aligned.m8n8.x4.shared.b16 [%0], {%1, %2, %3, %4};" ::"r"(addr), "r"(r0), "r"(r1), "r"(r2), "r"(r3) : "memory");
}
__device__ __forceinline__ uint32_t desc_lo(uint32_t addr, uint32_t lbo_bytes) { return ((addr & 0x3FFFF) >> 4) | ((lbo_bytes >> 4) << 16); }
__device__ __forceinline__ void mbar_arrive_pred(uint32_t bar, bool pred) {
    asm volatile("{\n.reg .pred p;\nsetp.ne.b32 p, %1, 0;\n@p mbarrier.arrive.shared::cta.b64 _, [%0];\n}" ::"r"(bar), "r"((int)pred) : "memory");
}
__device__ __forceinline__ void mbar_arrive_remote_pred(uint32_t cluster_addr, bool pred) {
    asm volatile("{\n.reg .pred p;\nsetp.ne.b32 p, %1, 0;\n@p mbarrier.arrive.shared::cluster.b64 _, [%0];\n}" ::"r"(cluster_addr), "r"((int)pred) : "memory");
}
__device__ __forceinline__ uint32_t mapa(uint32_t addr, uint32_t cta) { uint32_t r; asm("mapa.shared::cluster.u32 %0, %1, %2;" : "=r"(r) : "r"(addr), "r"(cta)); return r; }
__device__ __forceinline__ void e_expect_tx(uint32_t bar, uint32_t bytes) {
    asm volatile("{\n.reg .pred p;\nelect.sync _|p, 0xffffffff;\n@p mbarrier.arrive.expect_tx.shared::cta.b64 _, [%0], %1;\n}" ::"r"(bar), "r"(bytes) : "memory");
}
__device__ __forceinline__ void e_bulk_load(uint32_t dst, const void* src, uint32_t bytes, uint32_t bar) {
    asm volatile("{\n.reg .pred p;\nelect.sync _|p, 0xffffffff;\n@p cp.async.bulk.shared::cluster.global.mbarrier::complete_tx::bytes [%0], [%1], %2, [%3];\n}" ::"r"(dst), "l"(src), "r"(bytes), "r"(bar) : "memory");
}
__device__ __forceinline__ void e_bulk_load_mc(uint32_t dst, const void* src, uint32_t bytes, uint32_t bar, uint16_t mask) {
    asm volatile("{\n.reg .pred p;\nelect.sync _|p, 0xffffffff;\n@p cp.async.bulk.shared::cluster.global.mbarrier::complete_tx::bytes.multicast::cluster [%0], [%1], %2, [%3], %4;\n}" ::"r"(dst), "l"(src), "r"(bytes), "r"(bar), "h"(mask) : "memory");
}
__device__ __forceinline__ void e_bulk_load_hint(uint32_t dst, const void* src, uint32_t bytes, uint32_t bar, uint64_t pol) {
    asm volatile("{\n.reg .pred p;\nelect.sync _|p, 0xffffffff;\n@p cp.async.bulk.shared::cluster.global.mbarrier::complete_tx::bytes.L2::cache_hint [%0], [%1], %2, [%3], %4;\n}" ::"r"(dst), "l"(src), "r"(bytes), "r"(bar), "l"(pol) : "memory");
}
__device__ __forceinline__ void e_tma_load_2d(uint32_t dst, const CUtensorMap* map, int c0, int c1, uint32_t bar) {
    asm volatile("{\n.reg .pred p;\nelect.sync _|p, 0xffffffff;\n@p cp.async.bulk.tensor.2d.shared::cluster.global.mbarrier::complete_tx::bytes [%0], [%1, {%3, %4}], [%2];\n}" ::"r"(dst), "l"(map), "r"(bar), "r"(c0), "r"(c1) : "memory");
}
__device__ __forceinline__ void e_tma_prefetch_2d(const CUtensorMap* map, int c0, int c1) {
    asm volatile("{\n.reg .pred p;\nelect.sync _|p, 0xffffffff;\n@p cp.async.bulk.prefetch.tensor.2d.L2.global.tile [%0, {%1, %2}];\n}" ::"l"(map), "r"(c0), "r"(c1) : "memory");
}
__device__ __forceinline__ void e_red_add(unsigned* p) {
    asm volatile("{\n.reg .pred p;\nelect.sync _|p, 0xffffffff;\n@p red.relaxed.gpu.global.add.u32 [%0], 1;\n}" ::"l"(p) : "memory");
}
__device__ __forceinline__ void e_sts(uint32_t addr, int v) {
    asm volatile("{\n.reg .pred p;\nelect.sync _|p, 0xffffffff;\n@p st.volatile.shared.s32 [%0], %1;\n}" ::"r"(addr), "r"(v) : "memory");
}
__device__ __forceinline__ int lds_volatile(uint32_t addr) { int v; asm volatile("ld.volatile.shared.s32 %0, [%1];" : "=r"(v) : "r"(addr) : "memory"); return v; }
__device__ __forceinline__ void w_wait_sleep(uint32_t bar, uint32_t parity) {
    for (int n = 0; !mbar_test(bar, parity); n++) {
        __nanosleep(SLEEP_NS);
        if (n > 10000000 || *(volatile int*)&s_abort) { *(volatile int*)&s_abort = 1; break; }
    }
}
__device__ __forceinline__ void e_bulk_store(void* dst, uint32_t src, uint32_t bytes) {
    asm volatile("{\n.reg .pred p;\nelect.sync _|p, 0xffffffff;\n@p cp.async.bulk.global.shared::cta.bulk_group [%0], [%1], %2;\n}" ::"l"(dst), "r"(src), "r"(bytes) : "memory");
}
__device__ __forceinline__ void e_bulk_commit() {
    asm volatile("{\n.reg .pred p;\nelect.sync _|p, 0xffffffff;\n@p cp.async.bulk.commit_group;\n}" ::: "memory");
}
__device__ __forceinline__ void e_bulk_wait_all() {
    asm volatile("{\n.reg .pred p;\nelect.sync _|p, 0xffffffff;\n@p cp.async.bulk.wait_group 0;\n}" ::: "memory");
    __syncwarp();
}
__device__ __forceinline__ void e_prefetch_l2(const void* src, uint32_t bytes) {
    asm volatile("{\n.reg .pred p;\nelect.sync _|p, 0xffffffff;\n@p cp.async.bulk.prefetch.L2.global [%0], %1;\n}" ::"l"(src), "r"(bytes) : "memory");
}
__device__ __forceinline__ void sts64(uint32_t a, uint32_t x, uint32_t y) { asm volatile("st.shared.v2.u32 [%0], {%1, %2};" ::"r"(a), "r"(x), "r"(y) : "memory"); }
__device__ __forceinline__ int cta_x() { int v; asm volatile("mov.u32 %0, %%ctaid.x;" : "=r"(v)); return v; }
__device__ __forceinline__ void e_arrive(uint32_t bar) {
    asm volatile("{\n.reg .pred p;\nelect.sync _|p, 0xffffffff;\n@p mbarrier.arrive.shared::cta.b64 _, [%0];\n}" ::"r"(bar) : "memory");
}
template <int TB>
__device__ __forceinline__ void wgmma_ss_n128(float (&d)[64], uint64_t da, uint64_t db, int scale_d) {
    asm volatile("{\n.reg .pred p;\nsetp.ne.b32 p, %66, 0;\n"
        "wgmma.mma_async.sync.aligned.m64n128k16.f32.bf16.bf16 {"
        "%0, %1, %2, %3, %4, %5, %6, %7, %8, %9, %10, %11, %12, %13, %14, %15, "
        "%16, %17, %18, %19, %20, %21, %22, %23, %24, %25, %26, %27, %28, %29, %30, %31, "
        "%32, %33, %34, %35, %36, %37, %38, %39, %40, %41, %42, %43, %44, %45, %46, %47, "
        "%48, %49, %50, %51, %52, %53, %54, %55, %56, %57, %58, %59, %60, %61, %62, %63"
        "}, %64, %65, p, 1, 1, 0, %67;\n}\n"
        : "+f"(d[0]), "+f"(d[1]), "+f"(d[2]), "+f"(d[3]), "+f"(d[4]), "+f"(d[5]), "+f"(d[6]), "+f"(d[7]), "+f"(d[8]), "+f"(d[9]), "+f"(d[10]), "+f"(d[11]),
          "+f"(d[12]), "+f"(d[13]), "+f"(d[14]), "+f"(d[15]), "+f"(d[16]), "+f"(d[17]), "+f"(d[18]), "+f"(d[19]), "+f"(d[20]), "+f"(d[21]), "+f"(d[22]),
          "+f"(d[23]), "+f"(d[24]), "+f"(d[25]), "+f"(d[26]), "+f"(d[27]), "+f"(d[28]), "+f"(d[29]), "+f"(d[30]), "+f"(d[31]), "+f"(d[32]), "+f"(d[33]),
          "+f"(d[34]), "+f"(d[35]), "+f"(d[36]), "+f"(d[37]), "+f"(d[38]), "+f"(d[39]), "+f"(d[40]), "+f"(d[41]), "+f"(d[42]), "+f"(d[43]), "+f"(d[44]),
          "+f"(d[45]), "+f"(d[46]), "+f"(d[47]), "+f"(d[48]), "+f"(d[49]), "+f"(d[50]), "+f"(d[51]), "+f"(d[52]), "+f"(d[53]), "+f"(d[54]), "+f"(d[55]),
          "+f"(d[56]), "+f"(d[57]), "+f"(d[58]), "+f"(d[59]), "+f"(d[60]), "+f"(d[61]), "+f"(d[62]), "+f"(d[63])
        : "l"(da), "l"(db), "r"(scale_d), "n"(TB));
}

template <int TB>
__device__ __forceinline__ void wgmma_rs_n128(float (&d)[64], uint32_t a0, uint32_t a1, uint32_t a2, uint32_t a3, uint64_t db, int scale_d) {
    asm volatile("{\n.reg .pred p;\nsetp.ne.b32 p, %69, 0;\n"
        "wgmma.mma_async.sync.aligned.m64n128k16.f32.bf16.bf16 {"
        "%0, %1, %2, %3, %4, %5, %6, %7, %8, %9, %10, %11, %12, %13, %14, %15, "
        "%16, %17, %18, %19, %20, %21, %22, %23, %24, %25, %26, %27, %28, %29, %30, %31, "
        "%32, %33, %34, %35, %36, %37, %38, %39, %40, %41, %42, %43, %44, %45, %46, %47, "
        "%48, %49, %50, %51, %52, %53, %54, %55, %56, %57, %58, %59, %60, %61, %62, %63"
        "}, {%64, %65, %66, %67}, %68, p, 1, 1, %70;\n}\n"
        : "+f"(d[0]), "+f"(d[1]), "+f"(d[2]), "+f"(d[3]), "+f"(d[4]), "+f"(d[5]), "+f"(d[6]), "+f"(d[7]), "+f"(d[8]), "+f"(d[9]), "+f"(d[10]), "+f"(d[11]),
          "+f"(d[12]), "+f"(d[13]), "+f"(d[14]), "+f"(d[15]), "+f"(d[16]), "+f"(d[17]), "+f"(d[18]), "+f"(d[19]), "+f"(d[20]), "+f"(d[21]), "+f"(d[22]),
          "+f"(d[23]), "+f"(d[24]), "+f"(d[25]), "+f"(d[26]), "+f"(d[27]), "+f"(d[28]), "+f"(d[29]), "+f"(d[30]), "+f"(d[31]), "+f"(d[32]), "+f"(d[33]),
          "+f"(d[34]), "+f"(d[35]), "+f"(d[36]), "+f"(d[37]), "+f"(d[38]), "+f"(d[39]), "+f"(d[40]), "+f"(d[41]), "+f"(d[42]), "+f"(d[43]), "+f"(d[44]),
          "+f"(d[45]), "+f"(d[46]), "+f"(d[47]), "+f"(d[48]), "+f"(d[49]), "+f"(d[50]), "+f"(d[51]), "+f"(d[52]), "+f"(d[53]), "+f"(d[54]), "+f"(d[55]),
          "+f"(d[56]), "+f"(d[57]), "+f"(d[58]), "+f"(d[59]), "+f"(d[60]), "+f"(d[61]), "+f"(d[62]), "+f"(d[63])
        : "r"(a0), "r"(a1), "r"(a2), "r"(a3), "l"(db), "r"(scale_d), "n"(TB));
}

__device__ __forceinline__ uint32_t hfma2_bf16(uint32_t a, uint32_t b, uint32_t c) { uint32_t d; asm("fma.rn.bf16x2 %0, %1, %2, %3;" : "=r"(d) : "r"(a), "r"(b), "r"(c)); return d; }
__device__ __forceinline__ uint32_t hmul2_bf16(uint32_t a, uint32_t b) { uint32_t d; asm("mul.rn.bf16x2 %0, %1, %2;" : "=r"(d) : "r"(a), "r"(b)); return d; }
__device__ __forceinline__ uint32_t hsub2_bf16(uint32_t a, uint32_t b) { uint32_t d; asm("sub.rn.bf16x2 %0, %1, %2;" : "=r"(d) : "r"(a), "r"(b)); return d; }
__device__ __forceinline__ uint32_t dq_small(int a, int b, uint32_t zn, uint32_t sn) {
    return hmul2_bf16(hfma2_bf16(__byte_perm(a, b, 0x5410), 0x7F007F00u  , zn), sn);
}
__device__ __forceinline__ uint32_t k_scale(uint32_t k) {
    if (FIXMAX) return k;
    return hfma2_bf16(k, 0x3E033E03u  , hmul2_bf16(k, 0xB9D8B9D8u  ));
}
__device__ __forceinline__ uint32_t dq_any(int a, int b, uint32_t z, uint32_t s) {
    return hmul2_bf16(hsub2_bf16(pack_bf16(__int2float_rn(a), __int2float_rn(b)), z), s);
}
__device__ __forceinline__ uint64_t policy_evict_first() {
    uint64_t p;
    asm("createpolicy.fractional.L2::evict_first.b64 %0, 1.0;" : "=l"(p));
    return p;
}
__device__ __forceinline__ void bulk_load_hint(uint32_t dst, const void* src, uint32_t bytes, uint32_t bar, uint64_t pol) {
    asm volatile("cp.async.bulk.shared::cluster.global.mbarrier::complete_tx::bytes.L2::cache_hint [%0], [%1], %2, [%3], %4;" ::"r"(dst), "l"(src), "r"(bytes), "r"(bar), "l"(pol) : "memory");
}
__device__ __forceinline__ int4 lds128(uint32_t a) { int4 v; asm volatile("ld.shared.v4.s32 {%0, %1, %2, %3}, [%4];" : "=r"(v.x), "=r"(v.y), "=r"(v.z), "=r"(v.w) : "r"(a)); return v; }
__device__ __forceinline__ uint2 lds64(uint32_t a) { uint2 v; asm volatile("ld.shared.v2.u32 {%0, %1}, [%2];" : "=r"(v.x), "=r"(v.y) : "r"(a)); return v; }

struct Smem {
    uint8_t q[2][TILE_BYTES];
    uint8_t k[KST][TILE_BYTES];
    uint8_t v[VST][TILE_BYTES];
    uint8_t dq[DQ_WARPS][DQ_SLOTS][DQ_SLOT_BYTES];
    uint8_t dq_out[DQ_WARPS][JOB_ROWS * HD * 2];
    uint64_t q_full[2], q_empty[2], k_full[KST], k_empty[KST], v_full[VST], v_empty[VST];
    uint64_t dq_full[DQ_WARPS][DQ_SLOTS];
    uint64_t dq_done[DQ_WARPS][4];
    int published;
    uint64_t redo_full[2];
    int progress;
    int done;
};

constexpr float SCALE_LOG2 = 0.08838834764831845f * 1.4426950408889634f;
constexpr int BAR_PP0 = 1, BAR_EPI0 = 3, BAR_DONE = 5;

__device__ __forceinline__ void qk_gemm(float (&S)[64], uint64_t dq, uint64_t dk) {
#pragma unroll
    for (int s = 0; s < 8; s++) {
        const uint32_t off = ((s >> 2) * HALF_BYTES + (s & 3) * 32) >> 4;
        wgmma_ss_n128<0>(S, dq + off, dk + off, s != 0);
    }
}
__device__ __forceinline__ void pv_gemm(float (&O)[64], const uint32_t (&P)[32], uint64_t dv, int accumulate) {
#pragma unroll
    for (int s = 0; s < 8; s++) wgmma_rs_n128<1>(O, P[4 * s], P[4 * s + 1], P[4 * s + 2], P[4 * s + 3], dv + s * (2048 >> 4), s != 0 ? 1 : accumulate);
}
__device__ __forceinline__ void row_max(const float (&S)[64], float& m0, float& m1) {
    float a = fmaxf(S[0], S[1]), b = fmaxf(S[2], S[3]);
#pragma unroll
    for (int i = 1; i < 16; i++) { a = fmaxf(a, fmaxf(S[4 * i], S[4 * i + 1])); b = fmaxf(b, fmaxf(S[4 * i + 2], S[4 * i + 3])); }
    a = fmaxf(a, __shfl_xor_sync(0xffffffffu, a, 1)); b = fmaxf(b, __shfl_xor_sync(0xffffffffu, b, 1));
    a = fmaxf(a, __shfl_xor_sync(0xffffffffu, a, 2)); b = fmaxf(b, __shfl_xor_sync(0xffffffffu, b, 2));
    m0 = a; m1 = b;
}
__device__ __forceinline__ void exp_pack(const float (&S)[64], uint32_t (&P)[32], float nm0, float nm1, float& l0, float& l1) {
    float a0 = l0, b0 = l1, a1 = 0.f, b1 = 0.f;
#pragma unroll
    for (int i = 0; i < 32; i++) {
        float x0 = S[2 * i], x1 = S[2 * i + 1];
        if (FIXMAX) { const float nm = (i & 1) ? nm1 : nm0; x0 = fmaf(x0, SCALE_LOG2, nm); x1 = fmaf(x1, SCALE_LOG2, nm); }
        x0 = ex2(x0); x1 = ex2(x1);
        if (i & 1) { b0 += x0; b1 += x1; } else { a0 += x0; a1 += x1; }
        P[i] = pack_bf16(x0, x1);
    }
    l0 = a0 + a1; l1 = b0 + b1;
}
constexpr float L_MIN = 9.313225746154785e-10f  , L_MAX = 1073741824.0f  ;

__device__ __forceinline__ void finish_sums(float l0, float l1, float& i0, float& i1, int& bad) {
    l0 += __shfl_xor_sync(0xffffffffu, l0, 1); l1 += __shfl_xor_sync(0xffffffffu, l1, 1);
    l0 += __shfl_xor_sync(0xffffffffu, l0, 2); l1 += __shfl_xor_sync(0xffffffffu, l1, 2);
    asm("rcp.approx.ftz.f32 %0, %1;" : "=f"(i0) : "f"(l0));
    asm("rcp.approx.ftz.f32 %0, %1;" : "=f"(i1) : "f"(l1));
    bad = !(l0 >= L_MIN && l0 <= L_MAX && l1 >= L_MIN && l1 <= L_MAX);
}
__device__ __forceinline__ bool epilogue(const float (&O)[64], float i0, float i1, int bad, uint32_t stage_addr, const CUtensorMap* omap,
                                         int row0, int wg, int warp_in_wg, int lane) {
    const int m = lane >> 3;
    const int row = warp_in_wg * 16 + (m & 1) * 8 + (lane & 7);
    const uint32_t base = stage_addr + row * 128;
#pragma unroll
    for (int c = 0; c < 8; c++) {
        const int ch = 2 * c + (m >> 1);
        const uint32_t addr = base + (ch >> 3) * HALF_BYTES + (((ch & 7) ^ (row & 7)) << 4);
        stmatrix_x4(addr, pack_bf16(O[8 * c] * i0, O[8 * c + 1] * i0), pack_bf16(O[8 * c + 2] * i1, O[8 * c + 3] * i1),
                    pack_bf16(O[8 * c + 4] * i0, O[8 * c + 5] * i0), pack_bf16(O[8 * c + 6] * i1, O[8 * c + 7] * i1));
    }
    fence_async_smem();
    uint32_t any;
    asm volatile("{\n.reg .pred p, q;\nsetp.ne.b32 p, %1, 0;\nbar.red.or.pred q, %2, 128, p;\nselp.u32 %0, 1, 0, q;\n}" : "=r"(any) : "r"(bad), "r"(BAR_EPI0 + wg) : "memory");
    if (warp_in_wg == 3 && lane == 0) {
        tma_store_2d(omap, stage_addr, 0, row0);
        tma_store_2d(omap, stage_addr + HALF_BYTES, 64, row0);
        bulk_commit();
    }
    return any != 0;
}

constexpr int QBOX = 32;
struct Params {
    const char* codes[2];
    const char* zero[2];
    const char* scale[2];
    char* out[2];
    uint32_t desc_hi;
};

__device__ __forceinline__ void dq_stage(const Params& prm, unsigned kind, unsigned row, uint32_t dst, uint32_t bar) {
    uint64_t pol;
    asm volatile("createpolicy.fractional.L2::evict_first.b64 %0, 1.0;" : "=l"(pol));
    const uint32_t sbytes = kind ? JOB_ROWS * 2 : HD * 2;
    const unsigned soff = kind ? row * 2 : (row / GRP) * (HD * 2);
    e_expect_tx(bar, JOB_ROWS * HD * 4 + 2 * sbytes);
    e_bulk_load_hint(dst, prm.codes[kind] + (size_t)row * (HD * 4), JOB_ROWS * HD * 4, bar, pol);
    e_bulk_load(dst + JOB_ROWS * HD * 4, prm.zero[kind] + soff, sbytes, bar);
    e_bulk_load(dst + JOB_ROWS * HD * 4 + 256, prm.scale[kind] + soff, sbytes, bar);
}
__device__ __forceinline__ void e_load_q_piece(uint32_t qbuf, const CUtensorMap* qmap, int row0, int p, uint32_t bar) {
    e_tma_load_2d(qbuf + (p >> 2) * HALF_BYTES + (p & 3) * (QBOX * 128), qmap, (p >> 2) * 64, row0 + (p & 3) * QBOX, bar);
}
__device__ __forceinline__ unsigned unit_of(unsigned n) { return ((blockIdx.x + (n / NKV) * gridDim.x) / CTAS_PER_HEAD) * NKV + n % NKV; }

__global__ void __cluster_dims__(CLUSTER, 1, 1) __launch_bounds__(384, 1)
attn_kernel(const __grid_constant__ CUtensorMap qmap, const __grid_constant__ CUtensorMap omap, const __grid_constant__ Params prm) {
    extern __shared__ uint8_t smem_raw[];
    Smem& sm = *reinterpret_cast<Smem*>(smem_raw + ((1024 - (smem_u32(smem_raw) & 1023)) & 1023));
    const int tid = threadIdx.x;
    const int warp = __shfl_sync(0xffffffffu, tid >> 5, 0), lane = tid & 31;
    unsigned epoch = 0;
    if (warp == 0) asm volatile("ld.relaxed.gpu.global.u32 %0, [%1];" : "=r"(epoch) : "l"(&g_epoch) : "memory");
    if (warp >= 1 && warp <= DQ_WARPS) {
        const uint32_t bar0 = smem_u32(&sm.dq_full[warp - 1][0]);
        if (lane == 0) {
            for (int i = 0; i < DQ_SLOTS; i++) mbar_init(bar0 + i * 8, 1);
            asm volatile("fence.mbarrier_init.release.cluster;" ::: "memory");
        }
        __syncwarp();
        dq_stage(prm, warp - 1, unit_of(0) * BN + (blockIdx.x % CTAS_PER_HEAD) * JOB_ROWS, smem_u32(sm.dq[warp - 1][0]), bar0);
    }
    const int wgi = __shfl_sync(0xffffffffu, tid >> 7, 0);
    uint32_t cta_rank = 0;
    if (CLUSTER > 1) asm("mov.u32 %0, %%cluster_ctarank;" : "=r"(cta_rank));
    const int ntiles = (NUM_TILES - blockIdx.x + gridDim.x - 1) / gridDim.x;
    const int total = ntiles * NKV;

    if (tid == 0) {
        for (int i = 0; i < 2; i++) { mbar_init(smem_u32(&sm.q_full[i]), 1); mbar_init(smem_u32(&sm.q_empty[i]), 2); }
        for (int i = 0; i < 2; i++) mbar_init(smem_u32(&sm.redo_full[i]), 1);
        for (int i = 0; i < KST; i++) { mbar_init(smem_u32(&sm.k_full[i]), 1); mbar_init(smem_u32(&sm.k_empty[i]), 2 * CLUSTER); }
        for (int i = 0; i < VST; i++) { mbar_init(smem_u32(&sm.v_full[i]), 1); mbar_init(smem_u32(&sm.v_empty[i]), 2 * CLUSTER); }
        for (int i = 0; i < 2 * 4; i++) mbar_init(smem_u32(&sm.dq_done[0][0]) + i * 8, 1);
        sm.done = 0; sm.progress = 0; sm.published = 0; s_abort = 0;
        asm volatile("fence.mbarrier_init.release.cluster;" ::: "memory");
        const int row0 = blockIdx.x * BM;
        const uint32_t full = smem_u32(&sm.q_full[0]);
        mbar_expect_tx(full, TILE_BYTES);
        for (int p = 0; p < 8; p++) tma_load_2d(smem_u32(sm.q[0]) + (p >> 2) * HALF_BYTES + (p & 3) * (QBOX * 128), &qmap, (p >> 2) * 64, row0 + (p & 3) * QBOX, full);
    }
    asm volatile("barrier.cluster.arrive.relaxed.aligned;" ::: "memory");
    if (wgi == 0) {
        asm volatile("setmaxnreg.dec.sync.aligned.u32 %0;" ::"n"(PREGS));
        if (warp == 0) {
            asm volatile("barrier.cluster.wait.acquire.aligned;" ::: "memory");
            const unsigned target = (epoch + 1) * JOBS_PER_UNIT;
            const uint32_t progress = smem_u32(&sm.progress);
            const uint32_t kbuf = smem_u32(sm.k[0]) + cta_rank * (TILE_BYTES / CLUSTER), vbuf = smem_u32(sm.v[0]) + cta_rank * (TILE_BYTES / CLUSTER);
            const uint32_t kfull = smem_u32(&sm.k_full[0]), kempty = smem_u32(&sm.k_empty[0]), vfull = smem_u32(&sm.v_full[0]), vempty = smem_u32(&sm.v_empty[0]);
            auto head_of = [&](int t) { return (int)((blockIdx.x + t * gridDim.x) / CTAS_PER_HEAD); };
            auto probe = [&](int head) -> unsigned {
                unsigned v;
                asm volatile("ld.relaxed.gpu.global.u32 %0, [%1];" : "=r"(v) : "l"(g_flags + head * 32 + lane) : "memory");
                return __ballot_sync(0xffffffffu, (int)(v - target) >= 0);
            };
            auto acquire = [&]() {
                asm volatile("fence.acquire.gpu;" ::: "memory");
                asm volatile("fence.proxy.async.global;" ::: "memory");
            };
            auto refresh = [&](unsigned& mask, int head) { const unsigned m = probe(head); if (m != mask) { acquire(); mask = m; } };
            auto require = [&](unsigned& mask, int head, int bit) {
                if ((mask >> bit) & 1) return;
                for (int n = 0;; n++) {
                    mask = probe(head);
                    if ((mask >> bit) & 1) break;
                    __nanosleep(POLL_NS);
                    if (n > 4000000 || *(volatile int*)&s_abort) { *(volatile int*)&s_abort = 1; break; }
                }
                acquire();
            };
            auto issue = [&](uint32_t buf, const char* src, uint32_t full) {
                e_expect_tx(full, TILE_BYTES);
                if (CLUSTER > 1) e_bulk_load_mc(buf, src, TILE_BYTES / CLUSTER, full, (uint16_t)((1 << CLUSTER) - 1));
                else e_bulk_load(buf, src, TILE_BYTES, full);
            };
            int head = head_of(0), head_n = ntiles > 1 ? head_of(1) : head;
            unsigned cur = 0, nxt = 0;
            const char* kp = (const char*)g_kd + (size_t)head * NKV * TILE_BYTES + cta_rank * (TILE_BYTES / CLUSTER);
            const char* vp = (const char*)g_vd + (size_t)head * NKV * TILE_BYTES + cta_rank * (TILE_BYTES / CLUSTER);
            int kst = 0, kph = 1, vst = 0, vph = 1;
            require(cur, head, 0);
            issue(kbuf, kp, kfull); kp += TILE_BYTES; kst = 1 % KST; if (kst == 0) kph ^= 1;
            int it = 0;
#pragma unroll 1
            for (int t = 0; t < ntiles; t++) {
                const bool more = t + 1 < ntiles;
                const int qrow_n = (blockIdx.x + (t + 1) * gridDim.x) * BM;
#pragma unroll 1
                for (int j = 0; j < NKV; j++, it++) {
                    e_sts(progress, it);
                    if (j + 1 < NKV || more) {
                        if (j + 1 < NKV) require(cur, head, 2 * j + 2);
                        else { require(nxt, head_n, 0); kp = (const char*)g_kd + (size_t)head_n * NKV * TILE_BYTES + cta_rank * (TILE_BYTES / CLUSTER); }
                        w_wait_sleep(kempty + kst * 8, kph);
                        issue(kbuf + kst * TILE_BYTES, kp, kfull + kst * 8);
                        kp += TILE_BYTES;
                        if (++kst == KST) { kst = 0; kph ^= 1; }
                    }
                    require(cur, head, 2 * j + 1);
                    w_wait_sleep(vempty + vst * 8, vph);
                    issue(vbuf + vst * TILE_BYTES, vp, vfull + vst * 8);
                    vp += TILE_BYTES;
                    if (++vst == VST) { vst = 0; vph ^= 1; }
                    if (more && j >= 4 && j < 12) {
                        const uint32_t full = smem_u32(&sm.q_full[(t + 1) & 1]);
                        if (j == 4) {
                            w_wait_sleep(smem_u32(&sm.q_empty[(t + 1) & 1]), (((t + 1) >> 1) & 1) ^ 1);
                            e_expect_tx(full, TILE_BYTES);
                        }
                        e_load_q_piece(smem_u32(sm.q[(t + 1) & 1]), &qmap, qrow_n, j - 4, full);
                    }
                    if (cur != 0xffffffffu) refresh(cur, head);
                    else if (more && nxt != 0xffffffffu && j >= 8) refresh(nxt, head_n);
                }
                head = head_n; cur = nxt; nxt = 0;
                head_n = t + 2 < ntiles ? head_of(t + 2) : head;
                vp = (const char*)g_vd + (size_t)head * NKV * TILE_BYTES + cta_rank * (TILE_BYTES / CLUSTER);
            }
            e_sts(progress, 1 << 20);
            if (lane == 0 && atomicAdd(&g_ticket, 1) == gridDim.x - 1) { g_ticket = 0; *(volatile unsigned*)&g_epoch = target / JOBS_PER_UNIT; }
        } else if (warp <= DQ_WARPS) {
            const unsigned kind = warp - 1, sub = blockIdx.x % CTAS_PER_HEAD;
            const uint32_t ring = smem_u32(sm.dq[kind][0]), bar0 = smem_u32(&sm.dq_full[kind][0]), outb = smem_u32(sm.dq_out[kind]);
            const uint32_t done0 = smem_u32(&sm.dq_done[kind][0]);
            const uint32_t progress = smem_u32(&sm.progress), published = smem_u32(&sm.published);
            if (QMODE == 2) mbar_wait(bar0, 0);
            asm volatile("barrier.cluster.wait.acquire.aligned;" ::: "memory");
            if (QMODE == 2 && kind == 0) {
                const int row0 = blockIdx.x * BM;
                const uint32_t full = smem_u32(&sm.q_full[0]);
                e_expect_tx(full, TILE_BYTES);
                for (int p = 0; p < 8; p++) e_load_q_piece(smem_u32(sm.q[0]), &qmap, row0, p, full);
            }
            int stored = -1;
            auto retire = [&]() {
                if (stored >= 0) {
                    e_bulk_wait_all();
                    for (int n = 0; lds_volatile(published) < stored - 3; n++) {
                        __nanosleep(100);
                        if (n > 8000000 || *(volatile int*)&s_abort) { *(volatile int*)&s_abort = 1; break; }
                    }
                    e_arrive(done0 + (stored & 3) * 8);
                    stored = -1;
                }
            };
            const uint32_t ost = outb + (lane >> 4) * 1024 + (lane & 1) * 8 + (((lane & 15) >> 1) << 4);
            int issued = 1, islot = 1, slot = 0, phase = 0;
#pragma unroll 1
            for (int n = 0; n < total; n++) {
#pragma unroll 1
                while ((EARLY_STAGE || n > 0) && issued < total && issued < n + DQ_SLOTS) {
                    if (lds_volatile(progress) < issued - DQ_LEAD) {
                        if (issued > n) break;
                        retire();
                        for (int k = 0; lds_volatile(progress) < issued - DQ_LEAD; k++) {
                            __nanosleep(200);
                            if (k > 8000000 || *(volatile int*)&s_abort) { *(volatile int*)&s_abort = 1; break; }
                        }
                    }
                    dq_stage(prm, kind, unit_of(issued) * BN + sub * JOB_ROWS, ring + islot * DQ_SLOT_BYTES, bar0 + islot * 8);
                    issued++;
                    if (++islot == DQ_SLOTS) islot = 0;
                }
                const uint32_t src = ring + slot * DQ_SLOT_BYTES;
                mbar_wait(bar0 + slot * 8, phase);
                uint2 z = lds64(src + JOB_ROWS * HD * 4 + (kind ? 0 : lane * 8)), sc = lds64(src + JOB_ROWS * HD * 4 + 256 + (kind ? 0 : lane * 8));
                uint2 z2 = z, sc2 = sc;
                if (kind) { z2 = lds64(src + JOB_ROWS * HD * 4 + 8); sc2 = lds64(src + JOB_ROWS * HD * 4 + 256 + 8); }
#pragma unroll
                for (int hf = 0; hf < 2; hf++) {
                    int4 v[4];
#pragma unroll
                    for (int r = 0; r < 4; r++) v[r] = lds128(src + (hf * 4 + r) * 512 + lane * 16);
                    uint2 zz = hf ? z2 : z, ss = hf ? sc2 : sc;
                    int orv = 0;
#pragma unroll
                    for (int r = 0; r < 4; r++) orv |= v[r].x | v[r].y | v[r].z | v[r].w;
                    const bool small = __all_sync(0xffffffffu, (orv & ~255) == 0);
                    if (hf == 0) retire();
                    if (small) {
                        const uint32_t m6 = 0xBC80BC80u  , p6 = 0x42804280u  ;
                        zz.x = hmul2_bf16(zz.x, m6); zz.y = hmul2_bf16(zz.y, m6); ss.x = hmul2_bf16(ss.x, p6); ss.y = hmul2_bf16(ss.y, p6);
                        if (kind) {
#pragma unroll
                            for (int r = 0; r < 4; r++) {
                                const uint32_t zr = __byte_perm(r < 2 ? zz.x : zz.y, 0, (r & 1) ? 0x3232 : 0x1010);
                                const uint32_t sr = __byte_perm(r < 2 ? ss.x : ss.y, 0, (r & 1) ? 0x3232 : 0x1010);
                                sts64((ost ^ ((hf * 4 + r) << 4)) + (hf * 4 + r) * 128, dq_small(v[r].x, v[r].y, zr, sr), dq_small(v[r].z, v[r].w, zr, sr));
                            }
                        } else {
#pragma unroll
                            for (int r = 0; r < 4; r++)
                                sts64((ost ^ ((hf * 4 + r) << 4)) + (hf * 4 + r) * 128, k_scale(dq_small(v[r].x, v[r].y, zz.x, ss.x)), k_scale(dq_small(v[r].z, v[r].w, zz.y, ss.y)));
                        }
                    } else {
#pragma unroll
                        for (int r = 0; r < 4; r++) {
                            uint32_t z0 = zz.x, z1 = zz.y, s0 = ss.x, s1 = ss.y;
                            if (kind) {
                                z0 = z1 = __byte_perm(r < 2 ? zz.x : zz.y, 0, (r & 1) ? 0x3232 : 0x1010);
                                s0 = s1 = __byte_perm(r < 2 ? ss.x : ss.y, 0, (r & 1) ? 0x3232 : 0x1010);
                            }
                            uint32_t o0 = dq_any(v[r].x, v[r].y, z0, s0), o1 = dq_any(v[r].z, v[r].w, z1, s1);
                            if (!kind) { o0 = k_scale(o0); o1 = k_scale(o1); }
                            sts64((ost ^ ((hf * 4 + r) << 4)) + (hf * 4 + r) * 128, o0, o1);
                        }
                    }
                }
                fence_async_smem();
                __syncwarp();
                char* const gdst = prm.out[kind] + (size_t)unit_of(n) * TILE_BYTES + sub * (JOB_ROWS * 128);
                e_bulk_store(gdst, outb, 1024);
                e_bulk_store(gdst + HALF_BYTES, outb + 1024, 1024);
                e_bulk_commit();
                stored = n;
                if (n < STARTUP_JOBS) retire();
                if (++slot == DQ_SLOTS) { slot = 0; phase ^= 1; }
            }
            retire();
        } else {
            asm volatile("barrier.cluster.wait.acquire.aligned;" ::: "memory");
            const uint32_t done0 = smem_u32(&sm.dq_done[0][0]), published = smem_u32(&sm.published);
            int n = 0;
#pragma unroll 1
            while (n < total) {
                w_wait_sleep(done0 + (n & 3) * 8, (n >> 2) & 1);
                w_wait_sleep(done0 + 32 + (n & 3) * 8, (n >> 2) & 1);
                int m = 1;
                while (m < 3 && n + m < total && mbar_test(done0 + ((n + m) & 3) * 8, ((n + m) >> 2) & 1) &&
                       mbar_test(done0 + 32 + ((n + m) & 3) * 8, ((n + m) >> 2) & 1)) m++;
                asm volatile("fence.acq_rel.gpu;" ::: "memory");
                if (QMODE == 3 && n == 0) {
                    const uint32_t full = smem_u32(&sm.q_full[0]);
                    e_expect_tx(full, TILE_BYTES);
                    for (int p = 0; p < 8; p++) e_load_q_piece(smem_u32(sm.q[0]), &qmap, blockIdx.x * BM, p, full);
                }
                if (lane < 2 * m) asm volatile("red.relaxed.gpu.global.add.u32 [%0], 1;" ::"l"(g_flags + unit_of(n + (lane >> 1)) * 2 + (lane & 1)) : "memory");
                __syncwarp();
                n += m;
                e_sts(published, n);
            }
        }
    } else {
        asm volatile("setmaxnreg.inc.sync.aligned.u32 %0;" ::"n"(CREGS));
        asm volatile("barrier.cluster.wait.acquire.aligned;" ::: "memory");
        const int w = wgi - 1;
        const int warp_in_wg = warp & 3;
        const bool elected = (tid & 127) == 96;
        const bool sig_k = ((tid & 127) - 32u) < CLUSTER, sig_v = ((tid & 127) - 64u) < CLUSTER;
        const uint32_t sig_cta = tid & (CLUSTER - 1);
        const uint32_t k_empty_r = CLUSTER > 1 ? mapa(smem_u32(&sm.k_empty[0]), sig_cta) : smem_u32(&sm.k_empty[0]);
        const uint32_t v_empty_r = CLUSTER > 1 ? mapa(smem_u32(&sm.v_empty[0]), sig_cta) : smem_u32(&sm.v_empty[0]);
        const uint32_t k_full0 = smem_u32(&sm.k_full[0]), v_full0 = smem_u32(&sm.v_full[0]);
        const uint64_t dhi = (uint64_t)prm.desc_hi << 32;
        const uint64_t dk0 = dhi | desc_lo(smem_u32(sm.k[0]), 16), dv0 = dhi | desc_lo(smem_u32(sm.v[0]), HALF_BYTES);
        auto pp_sync = [&]() { if (PINGPONG) named_sync(BAR_PP0 + w, 256); };
        auto pp_arrive = [&]() { if (PINGPONG) named_arrive(BAR_PP0 + (w ^ 1), 256); };
        if (PINGPONG && w == 1) named_arrive(BAR_PP0, 256);

        static_assert(FIXMAX == 0, "the unified loop uses unshifted logits");
        float O[64], S[64];
        uint32_t PA[32], PB[32];
        float nm0 = 0.f, nm1 = 0.f, l0 = 0.f, l1 = 0.f;
        int lbad = 0;
        float lp0 = 1.f, lp1 = 1.f;
        int it = 0;
        int ks = 0, kph = 0;
        int vs = 0, vph = 0;
        uint32_t okk = 0, okv = 0;
        unsigned long long redo = 0;
        auto finish_step = [&](uint32_t (&Pc)[32], const bool has_pv) {
            const int ks_cur = ks, vs_cur = vs;
            if (++ks == KST) { ks = 0; kph ^= 1; }
            if (has_pv) { if (++vs == VST) { vs = 0; vph ^= 1; } }
            wg_wait<1>();
            pin(S);
            mbar_arrive_remote_pred(k_empty_r + ks_cur * 8, sig_k);
            okk = mbar_test(k_full0 + ks * 8, kph);
            exp_pack(S, Pc, nm0, nm1, l0, l1);
            pin(Pc);
            if (!okk && it != total - 1) { mbar_wait(k_full0 + ks * 8, kph); }
            okv = mbar_test(v_full0 + vs * 8, vph);
            wg_wait<0>();
            mbar_arrive_remote_pred(v_empty_r + vs_cur * 8, sig_v && has_pv);
            it++;
        };
        mbar_wait(k_full0, 0);
        uint64_t dq = 0;
        int t = 0;
#pragma unroll 1
        while (it < total) {
            const int j = it & (NKV - 1);
            if (j == 0) {
                dq = dhi | desc_lo(smem_u32(sm.q[t & 1]) + w * 8192, 16);
                mbar_wait(smem_u32(&sm.q_full[t & 1]), (t >> 1) & 1);
            }
            pp_sync();
            pin(S); wg_fence();
            qk_gemm(S, dq, dk0 + ks * (TILE_BYTES >> 4));
            wg_commit();
            if (it > 0) {
                if (!okv) { mbar_wait(v_full0 + vs * 8, vph); }
                pin(O); pin(PB); wg_fence();
                pv_gemm(O, PB, dv0 + vs * (TILE_BYTES >> 4), 1);
                wg_commit();
            } else {
                asm volatile("// no PV in the very first step" ::: "memory");
                wg_commit();
            }
            pp_arrive();
            if (j == 0) { finish_sums(l0, l1, lp0, lp1, lbad); l0 = 0.f; l1 = 0.f; }
            finish_step(PA, it > 0);
            pin(O); pin(PB);
            pp_sync();
            pin(S); wg_fence();
            qk_gemm(S, dq, dk0 + ks * (TILE_BYTES >> 4));
            wg_commit();
            const bool epi = j == 0 && t > 0;
            if (epi) {
                pp_arrive();
                if (epilogue(O, lp0, lp1, lbad, smem_u32(sm.q[(t - 1) & 1]) + w * 8192, &omap, (cta_x() + (t - 1) * gridDim.x) * BM + w * 64, w, warp_in_wg, lane))
                    redo |= 1ull << (t - 1);
            }
            if (!okv) { mbar_wait(v_full0 + vs * 8, vph); }
            pin(O); pin(PA); wg_fence();
            pv_gemm(O, PA, dv0 + vs * (TILE_BYTES >> 4), j != 0);
            wg_commit();
            if (!epi && (it != total - 1 || w == 0)) pp_arrive();
            finish_step(PB, true);
            pin(O); pin(PA);
            if (j == 2 && t > 0 && elected) { bulk_wait_read(); mbar_arrive(smem_u32(&sm.q_empty[(t - 1) & 1])); }
            if (j == NKV - 2) t++;
        }
        {
            if (!okv) mbar_wait(v_full0 + vs * 8, vph);
            pin(O); pin(PB); wg_fence();
            pv_gemm(O, PB, dv0 + vs * (TILE_BYTES >> 4), 1);
            wg_commit();
            finish_sums(l0, l1, lp0, lp1, lbad);
            wg_wait<0>();
            pin(O);
            mbar_arrive_remote_pred(v_empty_r + vs * 8, sig_v);
            if (epilogue(O, lp0, lp1, lbad, smem_u32(sm.q[(t - 1) & 1]) + w * 8192, &omap, (cta_x() + (t - 1) * gridDim.x) * BM + w * 64, w, warp_in_wg, lane))
                redo |= 1ull << (t - 1);
        }
        if (elected) bulk_wait_all();
        named_sync(BAR_DONE, 256);
        if (redo) {
            const uint32_t bar = smem_u32(&sm.redo_full[w]);
            const uint32_t qb = smem_u32(sm.q[w]), kb = smem_u32(sm.k[w]), vb = smem_u32(sm.v[w]);
            const bool issuer = (tid & 127) == 96;
            uint32_t phase = 0;
            for (int t = 0; t < ntiles; t++) {
                if (!((redo >> t) & 1)) continue;
                const int row0 = (cta_x() + t * gridDim.x) * BM, head = row0 / SEQ;
                float m0 = -INFINITY, m1 = -INFINITY, s0 = 0.f, s1 = 0.f;
#pragma unroll
                for (int i = 0; i < 64; i++) O[i] = 0.f;
                for (int j = 0; j < NKV; j++) {
                    if (issuer) {
                        unsigned f;
                        asm volatile("ld.acquire.gpu.global.u32 %0, [%1];" : "=r"(f) : "l"(g_flags + (head * NKV + j) * 2) : "memory");
                        asm volatile("ld.acquire.gpu.global.u32 %0, [%1];" : "=r"(f) : "l"(g_flags + (head * NKV + j) * 2 + 1) : "memory");
                        asm volatile("fence.proxy.async.global;" ::: "memory");
                        mbar_expect_tx(bar, (j == 0 ? 3 : 2) * TILE_BYTES);
                        if (j == 0) for (int p = 0; p < 8; p++) tma_load_2d(qb + (p >> 2) * HALF_BYTES + (p & 3) * (QBOX * 128), &qmap, (p >> 2) * 64, row0 + (p & 3) * QBOX, bar);
                        bulk_load(kb, (const char*)g_kd + (size_t)(head * NKV + j) * TILE_BYTES, TILE_BYTES, bar);
                        bulk_load(vb, (const char*)g_vd + (size_t)(head * NKV + j) * TILE_BYTES, TILE_BYTES, bar);
                    }
                    mbar_wait(bar, phase); phase ^= 1;
                    pin(S); wg_fence();
                    qk_gemm(S, dhi | desc_lo(qb + w * 8192, 16), dhi | desc_lo(kb, 16));
                    wg_commit(); wg_wait<0>(); pin(S);
                    constexpr float cs = FIXMAX ? SCALE_LOG2 : 1.0f;
                    float t0, t1; row_max(S, t0, t1);
                    t0 = fmaxf(m0, t0 * cs); t1 = fmaxf(m1, t1 * cs);
                    const float c0 = ex2(m0 - t0), c1 = ex2(m1 - t1);
                    m0 = t0; m1 = t1; s0 *= c0; s1 *= c1;
#pragma unroll
                    for (int i = 0; i < 16; i++) {
                        O[4 * i] *= c0; O[4 * i + 1] *= c0; O[4 * i + 2] *= c1; O[4 * i + 3] *= c1;
                        const float e0 = ex2(fmaf(S[4 * i], cs, -m0)), e1 = ex2(fmaf(S[4 * i + 1], cs, -m0));
                        const float e2 = ex2(fmaf(S[4 * i + 2], cs, -m1)), e3 = ex2(fmaf(S[4 * i + 3], cs, -m1));
                        s0 += e0 + e1; s1 += e2 + e3;
                        PA[2 * i] = pack_bf16(e0, e1); PA[2 * i + 1] = pack_bf16(e2, e3);
                    }
                    pin(O); pin(PA); wg_fence();
                    pv_gemm(O, PA, dhi | desc_lo(vb, HALF_BYTES), 1);
                    wg_commit(); wg_wait<0>(); pin(O);
                    named_sync(BAR_EPI0 + w, 128);
                }
                finish_sums(s0, s1, lp0, lp1, lbad);
                epilogue(O, lp0, lp1, 0, qb + w * 8192, &omap, row0 + w * 64, w, warp_in_wg, lane);
                if (issuer) bulk_wait_all();
                named_sync(BAR_EPI0 + w, 128);
            }
        }
    }
    if (CLUSTER > 1) asm volatile("barrier.cluster.arrive.relaxed.aligned;\nbarrier.cluster.wait.aligned;" ::: "memory");
}

typedef CUresult (*EncodeTiledFn)(CUtensorMap*, CUtensorMapDataType, cuuint32_t, void*, const cuuint64_t*, const cuuint64_t*, const cuuint32_t*,
                                  const cuuint32_t*, CUtensorMapInterleave, CUtensorMapSwizzle, CUtensorMapL2promotion, CUtensorMapFloatOOBfill);

CUtensorMap make_map(EncodeTiledFn fn, void* ptr, uint32_t box_rows) {
    CUtensorMap m;
    cuuint64_t dims[2] = {(cuuint64_t)HD, (cuuint64_t)NH * SEQ};
    cuuint64_t strides[1] = {(cuuint64_t)HD * 2};
    cuuint32_t box[2] = {64, box_rows};
    cuuint32_t estr[2] = {1, 1};
    fn(&m, CU_TENSOR_MAP_DATA_TYPE_BFLOAT16, 2, ptr, dims, strides, box, estr, CU_TENSOR_MAP_INTERLEAVE_NONE, CU_TENSOR_MAP_SWIZZLE_128B,
       CU_TENSOR_MAP_L2_PROMOTION_L2_256B, CU_TENSOR_MAP_FLOAT_OOB_FILL_NONE);
    return m;
}

}

extern "C" void kernel_launch(void* const* d_in, const int* in_sizes, int n_in, void* d_out, int out_size) {
    (void)in_sizes; (void)n_in; (void)out_size;
    static EncodeTiledFn encode = nullptr;
    static int grid = 0;
    static char *kd_ptr = nullptr, *vd_ptr = nullptr;
    constexpr int smem_bytes = (int)sizeof(Smem) + 1024;
    if (!encode) {
        void* fn = nullptr;
        cudaDriverEntryPointQueryResult qr;
        cudaGetDriverEntryPoint("cuTensorMapEncodeTiled", &fn, cudaEnableDefault, &qr);
        encode = (EncodeTiledFn)fn;
        cudaGetSymbolAddress((void**)&kd_ptr, g_kd);
        cudaGetSymbolAddress((void**)&vd_ptr, g_vd);
        cudaFuncSetAttribute(attn_kernel, cudaFuncAttributeMaxDynamicSharedMemorySize, smem_bytes);
        int sms = 0;
        cudaDeviceGetAttribute(&sms, cudaDevAttrMultiProcessorCount, 0);
        cudaLaunchConfig_t cfg = {};
        cfg.gridDim = dim3((sms / CLUSTER) * CLUSTER); cfg.blockDim = dim3(384); cfg.dynamicSmemBytes = smem_bytes;
        cudaLaunchAttribute at; at.id = cudaLaunchAttributeClusterDimension; at.val.clusterDim.x = CLUSTER; at.val.clusterDim.y = 1; at.val.clusterDim.z = 1;
        cfg.attrs = &at; cfg.numAttrs = 1;
        int nc = 0;
        if (cudaOccupancyMaxActiveClusters(&nc, attn_kernel, &cfg) != cudaSuccess || nc <= 0) { nc = sms / CLUSTER; (void)cudaGetLastError(); }
        grid = (nc * CLUSTER < sms ? nc * CLUSTER : sms) / CTAS_PER_HEAD * CTAS_PER_HEAD;
        if (grid > NUM_TILES) grid = NUM_TILES;
    }
    const CUtensorMap qmap = make_map(encode, d_in[0], QBOX);
    const CUtensorMap omap = make_map(encode, d_out, 64);
    Params prm;
    prm.codes[0] = (const char*)d_in[1]; prm.codes[1] = (const char*)d_in[2];
    prm.scale[0] = (const char*)d_in[3]; prm.zero[0] = (const char*)d_in[4];
    prm.scale[1] = (const char*)d_in[5]; prm.zero[1] = (const char*)d_in[6];
    prm.out[0] = kd_ptr; prm.out[1] = vd_ptr;
    prm.desc_hi = 0x40000040u;
    attn_kernel<<<grid, 384, smem_bytes>>>(qmap, omap, prm);
}
```
